```python
import torch

def _softmax(x, axis=-1):
    return torch.softmax(x, dim=axis)
def _gelu(x):
    return torch.nn.functional.gelu(x, approximate="tanh")
def _silu(x):
    return torch.nn.functional.silu(x)
def _sigmoid(x):
    return torch.sigmoid(x)
def _layernorm(x, axis=-1, eps=1e-5):
    m = x.mean(dim=axis, keepdim=True)
    v = x.var(dim=axis, keepdim=True, unbiased=False)
    return (x - m) / torch.sqrt(v + eps)
def _scatter_add(tgt, idx, src, axis=0):
    return tgt.clone().index_add_(axis, idx, src)
def _segment_sum(src, seg, n):
    out = torch.zeros((n,) + src.shape[1:], dtype=src.dtype)
    return out.index_add_(0, seg, src)
def _pad(x, pw):
    flat = tuple(v for pair in reversed(pw) for v in pair)
    return torch.nn.functional.pad(x, flat)

kernel_name = 'gated_mix__mha_block_cached__dense_activation_silu__decode'

def setup_inputs():

    _w = (lambda a: (lambda t: t.to(torch.bfloat16) if t.is_floating_point() else t)(torch.as_tensor(a)))
    def _A_setup():
        B, Sq, D = 8, 1, 576
        H, Sk, Dh = 32, 4096, 128
        return {
            "x": _w((lambda *s: torch.randn(*s, dtype=torch.bfloat16) * 0.1)(B, Sq, D)),
            "k_cache": _w((lambda *s: torch.randn(*s, dtype=torch.bfloat16) * 3.2)(B, H, Sk, Dh)),
            "v_cache": _w((lambda *s: torch.randn(*s, dtype=torch.bfloat16) * 3.2)(B, H, Sk, Dh)),
            "wq": _w((lambda *s: torch.randn(*s, dtype=torch.bfloat16) * 3.2)(D, H * Dh) * (D ** -0.5)),
            "wo": _w((lambda *s: torch.randn(*s, dtype=torch.bfloat16) * 3.2)(H * Dh, D) * ((H * Dh) ** -0.5)),
        }
    _A_in = _A_setup()

    def _B_setup():
        B, S, D, F = 8, 1, 576, 4608
        return {
            "x": _w((lambda *s: torch.randn(*s, dtype=torch.bfloat16) * 0.1)(B, S, D)),
            "w1": _w((lambda *s: torch.randn(*s, dtype=torch.bfloat16) * 3.2)(D, F) * (D ** -0.5)),
            "w2": _w((lambda *s: torch.randn(*s, dtype=torch.bfloat16) * 3.2)(F, D) * (F ** -0.5)),
        }
    _B_in = _B_setup()

    return {
        "A_x": _A_in["x"],
        "A_k_cache": _A_in["k_cache"],
        "A_v_cache": _A_in["v_cache"],
        "A_wq": _A_in["wq"],
        "A_wo": _A_in["wo"],
        "B_x": _B_in["x"],
        "B_w1": _B_in["w1"],
        "B_w2": _B_in["w2"],
        "gate_w": _w((lambda *s: torch.randn(*s, dtype=torch.bfloat16) * 0.1)(576) * 16.0),
    }

def reference(A_x, A_k_cache, A_v_cache, A_wq, A_wo, B_x, B_w1, B_w2, gate_w):
    def _A_ref(x, k_cache, v_cache, wq, wo):
        B, Sq, D = x.shape
        H, Dh = 32, 128
        q = (lambda x, *d: x.permute(*d))((x @ wq).reshape(B, Sq, H, Dh), 0, 2, 1, 3)
        scores = torch.einsum("bhqd,bhkd->bhqk", q, k_cache) * (Dh ** -0.5)
        p = _softmax(scores, axis=-1)
        o = torch.einsum("bhqk,bhkd->bhqd", p, v_cache)
        return (lambda x, *d: x.permute(*d))(o, 0, 2, 1, 3).reshape(B, Sq, H * Dh) @ wo

    def _B_ref(x, w1, w2):
        h = torch.einsum("bsd,df->bsf", x, w1)
        h = _silu(h)
        out = torch.einsum("bsf,fd->bsd", h, w2)
        return out

    x = A_x
    g = _sigmoid((x * gate_w).sum(-1, keepdims=True))
    a = _A_ref(x, A_k_cache, A_v_cache, A_wq, A_wo)
    b = _B_ref(x, B_w1, B_w2)
    return g * a + (1 - g) * b
```

```cpp
#include <cuda_runtime.h>
#include <cuda_bf16.h>
#include <cuda.h>
#include <stdint.h>

namespace {

constexpr int NB = 8, DM = 576, NH = 32, SK = 4096, DH = 128, FF = 4608;
constexpr int TKEYS = 128;
constexpr int TILE_BYTES = TKEYS * DH * 2;
constexpr int UPP = SK / TKEYS;
constexpr int NU = NB * NH * UPP;
constexpr int NCTA = 132, NOWN = 128;
constexpr int NTHREADS = 416;
#define NSTATIC 4
#define NTOP 1
#define NPACE 5
#define TMPF 300
#define QPRE 36
#define QFIRST 1
#define PACE_T0 1200
#define PACE_DT 1400
#define WTHRESH 0
#define CMARGIN 528
constexpr int QCOLS = 144;
constexpr int WBOX = QCOLS + 8;
constexpr int WPITCH = WBOX * 2;
constexpr int WO_BYTES = DH * WPITCH;
constexpr int W2_BYTES = QCOLS * WPITCH;
constexpr int OS_PITCH = 272, HS_PITCH = 304;

constexpr int SM_RING = 0;
constexpr int SM_WO   = 4 * TILE_BYTES;
constexpr int SM_W2   = SM_WO + WO_BYTES;
constexpr int SM_Q    = SM_W2 + W2_BYTES;
constexpr int SM_PART = SM_Q + 512;
constexpr int SM_ML   = SM_PART + 2 * 8 * 128 * 4;
constexpr int SM_OS   = SM_ML + 128;
constexpr int SM_HS   = SM_OS + 8 * OS_PITCH;
constexpr int SM_COMB = SM_HS + 8 * HS_PITCH;
constexpr int SM_G    = SM_COMB + 2 * 4 * 128 * 4;
constexpr int SM_BAR  = SM_G + 32;
constexpr int SM_MISC = SM_BAR + 16 * 8;
constexpr int SM_TOTAL = SM_MISC + 32;
constexpr int SM_RED  = SM_PART;
static_assert(SM_TOTAL <= 232448, "smem");
static_assert(SM_RED + 12 * 256 * 4 <= SM_COMB, "red scratch");

struct __align__(128) Sync { unsigned v; unsigned pad[31]; };
__device__ Sync g_ticket, g_epoch;
__device__ __align__(128) unsigned g_q[NB * NH * DH];
__device__ __align__(128) unsigned g_h[NB * FF];
__device__ __align__(128) unsigned g_po[NU * DH];
__device__ __align__(128) unsigned g_lse[NU * 8];
__device__ __align__(128) float4 g_acc[4 * 9 * 2 * 32];

#define TR(i) do { } while (0)
#define TRDUMP(i) do { } while (0)
#define SM_EXTRA 0

__device__ __forceinline__ unsigned gtime32() { unsigned t; asm volatile("mov.u32 %0, %globaltimer_lo;" : "=r"(t)); return t; }
constexpr long long SPIN_LIMIT = 4000000000LL;

__device__ __forceinline__ void mbar_init(uint32_t bar, uint32_t cnt) {
    asm volatile("mbarrier.init.shared::cta.b64 [%0], %1;" ::"r"(bar), "r"(cnt) : "memory");
}
__device__ __forceinline__ void mbar_expect_tx(uint32_t bar, uint32_t bytes) {
    asm volatile("mbarrier.arrive.expect_tx.shared::cta.b64 _, [%0], %1;" ::"r"(bar), "r"(bytes) : "memory");
}
__device__ __forceinline__ void mbar_arrive(uint32_t bar) {
    asm volatile("mbarrier.arrive.shared::cta.b64 _, [%0];" ::"r"(bar) : "memory");
}
__device__ __forceinline__ bool mbar_try(uint32_t bar, uint32_t parity) {
    uint32_t ok;
    asm volatile("{\n.reg .pred p;\nmbarrier.try_wait.parity.shared::cta.b64 p, [%1], %2;\nselp.u32 %0, 1, 0, p;\n}"
                 : "=r"(ok) : "r"(bar), "r"(parity) : "memory");
    return ok != 0;
}
__device__ __forceinline__ bool mbar_test(uint32_t bar, uint32_t parity) {
    uint32_t ok;
    asm volatile("{\n.reg .pred p;\nmbarrier.test_wait.parity.shared::cta.b64 p, [%1], %2;\nselp.u32 %0, 1, 0, p;\n}"
                 : "=r"(ok) : "r"(bar), "r"(parity) : "memory");
    return ok != 0;
}
__device__ __forceinline__ void mbar_wait(uint32_t bar, uint32_t parity) {
    if (mbar_try(bar, parity)) return;
    long long t0 = clock64();
    while (!mbar_try(bar, parity)) {
        if (clock64() - t0 > SPIN_LIMIT) __trap();
    }
}
__device__ __forceinline__ void bulk_g2s(uint32_t dst, const void* src, uint32_t bytes, uint32_t bar) {
    asm volatile("cp.async.bulk.shared::cluster.global.mbarrier::complete_tx::bytes [%0], [%1], %2, [%3];"
                 ::"r"(dst), "l"(src), "r"(bytes), "r"(bar) : "memory");
}
__device__ __forceinline__ void bulk_g2s_hint(uint32_t dst, const void* src, uint32_t bytes, uint32_t bar, uint64_t pol) {
    asm volatile("cp.async.bulk.shared::cluster.global.mbarrier::complete_tx::bytes.L2::cache_hint [%0], [%1], %2, [%3], %4;"
                 ::"r"(dst), "l"(src), "r"(bytes), "r"(bar), "l"(pol) : "memory");
}
__device__ __forceinline__ void bulk_prefetch_l2(const void* src, uint32_t bytes) {
    asm volatile("cp.async.bulk.prefetch.L2.global [%0], %1;" ::"l"(src), "r"(bytes) : "memory");
}
__device__ __forceinline__ void tma_2d(uint32_t dst, const CUtensorMap* tm, int c0, int c1, uint32_t bar, uint64_t pol) {
    asm volatile("cp.async.bulk.tensor.2d.shared::cluster.global.mbarrier::complete_tx::bytes.L2::cache_hint [%0], [%1, {%3, %4}], [%2], %5;"
                 ::"r"(dst), "l"(tm), "r"(bar), "r"(c0), "r"(c1), "l"(pol) : "memory");
}
__device__ __forceinline__ void bar_sync(int id, int n) { asm volatile("bar.sync %0, %1;" ::"r"(id), "r"(n) : "memory"); }
__device__ __forceinline__ void bar_arrive(int id, int n) { asm volatile("bar.arrive %0, %1;" ::"r"(id), "r"(n) : "memory"); }
__device__ __forceinline__ void ldsm4(uint32_t (&r)[4], uint32_t a) {
    asm volatile("ldmatrix.sync.aligned.m8n8.x4.shared.b16 {%0,%1,%2,%3}, [%4];"
                 : "=r"(r[0]), "=r"(r[1]), "=r"(r[2]), "=r"(r[3]) : "r"(a) : "memory");
}
__device__ __forceinline__ void ldsm4t(uint32_t (&r)[4], uint32_t a) {
    asm volatile("ldmatrix.sync.aligned.m8n8.x4.trans.shared.b16 {%0,%1,%2,%3}, [%4];"
                 : "=r"(r[0]), "=r"(r[1]), "=r"(r[2]), "=r"(r[3]) : "r"(a) : "memory");
}
__device__ __forceinline__ void mma16816(float (&c)[4], const uint32_t (&a)[4], uint32_t b0, uint32_t b1) {
    asm volatile("mma.sync.aligned.m16n8k16.row.col.f32.bf16.bf16.f32 {%0,%1,%2,%3}, {%4,%5,%6,%7}, {%8,%9}, {%0,%1,%2,%3};"
                 : "+f"(c[0]), "+f"(c[1]), "+f"(c[2]), "+f"(c[3])
                 : "r"(a[0]), "r"(a[1]), "r"(a[2]), "r"(a[3]), "r"(b0), "r"(b1));
}
__device__ __forceinline__ uint32_t lds32(uint32_t a) {
    uint32_t v; asm volatile("ld.shared.u32 %0, [%1];" : "=r"(v) : "r"(a) : "memory"); return v;
}
__device__ __forceinline__ uint2 ldg64_stream(const void* p) {
    uint2 v; asm volatile("ld.global.nc.L1::no_allocate.v2.u32 {%0,%1}, [%2];" : "=r"(v.x), "=r"(v.y) : "l"(p)); return v;
}
__device__ __forceinline__ unsigned ld_relaxed(const unsigned* p) {
    unsigned v; asm volatile("ld.relaxed.gpu.global.u32 %0, [%1];" : "=r"(v) : "l"(p) : "memory"); return v;
}
__device__ __forceinline__ unsigned ld_acquire(const unsigned* p) {
    unsigned v; asm volatile("ld.acquire.gpu.global.u32 %0, [%1];" : "=r"(v) : "l"(p) : "memory"); return v;
}
__device__ __forceinline__ uint4 ld_relaxed4(const void* p) {
    uint4 v; asm volatile("ld.relaxed.gpu.global.v4.u32 {%0,%1,%2,%3}, [%4];"
                          : "=r"(v.x), "=r"(v.y), "=r"(v.z), "=r"(v.w) : "l"(p) : "memory"); return v;
}
__device__ __forceinline__ void st_relaxed(unsigned* p, unsigned v) {
    asm volatile("st.relaxed.gpu.global.u32 [%0], %1;" ::"l"(p), "r"(v) : "memory");
}
__device__ __forceinline__ float ex2(float x) { float y; asm("ex2.approx.ftz.f32 %0, %1;" : "=f"(y) : "f"(x)); return y; }
__device__ __forceinline__ uint32_t pack_bf16(float lo, float hi) {
    uint32_t r; asm("cvt.rn.bf16x2.f32 %0, %1, %2;" : "=r"(r) : "f"(hi), "f"(lo)); return r;
}
__device__ __forceinline__ float bf16_round(float x) { return __bfloat162float(__float2bfloat16_rn(x)); }
__device__ __forceinline__ float warp_max(float x) {
    int b = __float_as_int(x);
    b ^= (b >> 31) & 0x7fffffff;
    b = __reduce_max_sync(0xffffffffu, b);
    b ^= (b >> 31) & 0x7fffffff;
    return __int_as_float(b);
}
__device__ __forceinline__ bool tags16_ok(const uint4& v, unsigned tag) {
    return (((v.x ^ tag) | (v.y ^ tag) | (v.z ^ tag) | (v.w ^ tag)) & 0xffffu) == 0;
}
__device__ __forceinline__ uint2 settle_tagged(uint4 v, const unsigned* p, unsigned tag) {
    if (!tags16_ok(v, tag)) {
        long long t0 = clock64();
        do {
            v = ld_relaxed4(p);
            if (clock64() - t0 > SPIN_LIMIT) __trap();
        } while (!tags16_ok(v, tag));
    }
    return make_uint2(__byte_perm(v.x, v.y, 0x7632), __byte_perm(v.z, v.w, 0x7632));
}
__device__ __forceinline__ unsigned tag_bf16(float x, unsigned tag) {
    return ((unsigned)__bfloat16_as_ushort(__float2bfloat16_rn(x)) << 16) | tag;
}

struct Slice { uint2 w[3][4]; };
__device__ __forceinline__ void slice_load(Slice& s, const __nv_bfloat16* W, int ld, int col0, int warp, int g, int t) {
    const __nv_bfloat16* p = W + (size_t)(48 * warp + 4 * t) * ld + col0 + 4 * g;
#pragma unroll
    for (int k = 0; k < 3; k++)
#pragma unroll
        for (int i = 0; i < 4; i++) s.w[k][i] = ldg64_stream(p + (size_t)(16 * k + i) * ld);
}
__device__ __forceinline__ void slice_mma(const Slice& s, const uint2 (&xf)[3], float (&c0)[4], float (&c1)[4]) {
#pragma unroll
    for (int k = 0; k < 3; k++) {
        uint32_t a[4];
        a[0] = __byte_perm(s.w[k][0].x, s.w[k][1].x, 0x5410); a[1] = __byte_perm(s.w[k][0].x, s.w[k][1].x, 0x7632);
        a[2] = __byte_perm(s.w[k][2].x, s.w[k][3].x, 0x5410); a[3] = __byte_perm(s.w[k][2].x, s.w[k][3].x, 0x7632);
        mma16816(c0, a, xf[k].x, xf[k].y);
        a[0] = __byte_perm(s.w[k][0].y, s.w[k][1].y, 0x5410); a[1] = __byte_perm(s.w[k][0].y, s.w[k][1].y, 0x7632);
        a[2] = __byte_perm(s.w[k][2].y, s.w[k][3].y, 0x5410); a[3] = __byte_perm(s.w[k][2].y, s.w[k][3].y, 0x7632);
        mma16816(c1, a, xf[k].x, xf[k].y);
    }
}
__device__ __forceinline__ void slice_store(const float (&c0)[4], const float (&c1)[4], float* red, int g, int t) {
    *reinterpret_cast<float4*>(red + (2 * t) * 32 + 4 * g) = make_float4(c0[0], c0[2], c1[0], c1[2]);
    *reinterpret_cast<float4*>(red + (2 * t + 1) * 32 + 4 * g) = make_float4(c0[1], c0[3], c1[1], c1[3]);
}

__global__ void __launch_bounds__(NTHREADS, 1)
fused_kernel(const __nv_bfloat16* __restrict__ x, const __nv_bfloat16* __restrict__ kc, const __nv_bfloat16* __restrict__ vc,
             const __nv_bfloat16* __restrict__ w1, const __nv_bfloat16* __restrict__ gate_w,
             __nv_bfloat16* __restrict__ out, const uint32_t zero,
             const __grid_constant__ CUtensorMap tm_wq, const __grid_constant__ CUtensorMap tm_wo,
             const __grid_constant__ CUtensorMap tm_w2)
{
    extern __shared__ __align__(1024) uint8_t smem[];
    const uint32_t sb = (uint32_t)__cvta_generic_to_shared(smem);
    const int tid = threadIdx.x, warp = tid >> 5, lane = tid & 31, g = lane >> 2, t = lane & 3;
    const int cta = blockIdx.x;
    const bool owner = cta < NOWN;
    const int head = cta >> 2, quart = cta & 3;
    const uint32_t bar_full = sb + SM_BAR, bar_empty = bar_full + 32, bar_w = bar_full + 64, bar_q = bar_full + 80;
    volatile int* s_unit = reinterpret_cast<volatile int*>(smem + SM_MISC);
    volatile int* s_front = s_unit + 2;
    constexpr float SCL = 0.08838834764831845f * 1.4426950408889634f;

    unsigned tag = 0, tag16 = 0;
    uint64_t pol;
    asm volatile("createpolicy.fractional.L2::evict_first.b64 %0, 1.0;" : "=l"(pol));
    if (warp < 3 && lane == 0 && owner) {
        mbar_init(bar_q + 8 * warp, 1);
        asm volatile("fence.mbarrier_init.release.cluster;" ::: "memory");
        mbar_expect_tx(bar_q + 8 * warp, 192 * 64);
        tma_2d(sb + SM_WO + warp * (192 * 64), &tm_wq, cta * 32, warp * 192, bar_q + 8 * warp, pol);
        if (warp == 0) TR(16);
    }
    const char* kb = reinterpret_cast<const char*>(kc);
    const char* vb = reinterpret_cast<const char*>(vc);
    auto issue = [&](int slot, const char* src) {
        mbar_expect_tx(bar_full + 8 * slot, TILE_BYTES);
        bulk_g2s_hint(sb + SM_RING + slot * TILE_BYTES, src, TILE_BYTES, bar_full + 8 * slot, pol);
    };
    if (warp >= 4 && warp < 8 && lane == 0) {
        const int i = warp - 4;
        mbar_init(bar_full + 8 * i, (i & 1) ? 1 : 2);
        asm volatile("fence.mbarrier_init.release.cluster;" ::: "memory");
        if (i < NTOP) { issue(i, ((i & 1) ? vb : kb) + (size_t)(cta + (i >> 1) * NCTA) * TILE_BYTES); TR(18 + i); }
    }
    const unsigned t_start = gtime32();
    if (warp == 12 && lane == 0) {
        TR(0);
#pragma unroll
        for (int s = 0; s < 4; s++) mbar_init(bar_empty + 8 * s, 8);
        mbar_init(bar_w, 1);
        mbar_init(bar_w + 8, 1);
        asm volatile("fence.mbarrier_init.release.cluster;" ::: "memory");
        *s_front = 0;
        s_unit[0] = cta;
        s_unit[1] = cta + NCTA;
    }
    if (warp == 0 && cta < QPRE) st_relaxed(g_q + cta * 32 + lane, 0u);
    __syncwarp();
    bar_sync(1, 416);
    if (warp == 12) {
        if (lane == 0) {
#pragma unroll 1
            for (int i = NTOP; i < NPACE; i++) {
                while ((int)(gtime32() - t_start) < PACE_T0 + (i - NTOP) * PACE_DT) { }
                if (i < 4) issue(i, ((i & 1) ? vb : kb) + (size_t)(cta + (i >> 1) * NCTA) * TILE_BYTES);
                else if (i == 4) { if (owner) bulk_prefetch_l2(reinterpret_cast<const char*>(w1) + cta * (DM * FF * 2 / NOWN), DM * FF * 2 / NOWN); }
                else {
                    if (mbar_test(bar_empty, 0)) break;
                    bulk_prefetch_l2((((i - 1) & 1) ? vb : kb) + (size_t)(cta + ((i - 1) >> 1) * NCTA) * TILE_BYTES, TILE_BYTES);
                }
                TR(18 + i);
            }
            TR(1);
        }
        __syncwarp();
    }

#pragma unroll 1
    for (int pass = 0; pass < 2; pass++) {
    if (pass == 1 && warp == 12) {
        const unsigned epoch = ld_relaxed(&g_epoch.v) + 1;
        tag16 = (epoch & 0x7fffu) | 0x8000u;
        __syncwarp();
        bool w_done = !owner;
        for (int it = 2;; it++) {
            const int s = it & 1;
            const uint32_t ph = ((it >> 1) & 1) ^ 1;
            int u = 0;
            if (lane == 0) {
                mbar_wait(bar_empty + 16 * s, ph);
                if (it < NSTATIC) u = cta + it * NCTA;
                else {
                    const unsigned tk = atomicAdd(&g_ticket.v, 1u);
                    u = (int)tk + NSTATIC * NCTA;
                    if (tk == NU - NSTATIC * NCTA + NCTA - 1) {
                        st_relaxed(&g_ticket.v, 0u);
                        st_relaxed(&g_epoch.v, epoch);
                    }
                }
                s_unit[s] = (u < NU) ? u : -1;
                *s_front = (u < NU) ? u : 0x7fffffff;
            }
            u = __shfl_sync(0xffffffffu, u, 0);
            const unsigned* qp = g_q + (u / UPP) * DH + lane * 4;
            uint4 qv = make_uint4(0u, 0u, 0u, 0u);
            if (u < NU) qv = ld_relaxed4(qp);
            if (lane == 0) {
                if (u < NU) {
                    issue(2 * s, kb + (size_t)u * TILE_BYTES);
                    mbar_wait(bar_empty + 16 * s + 8, ph);
                    issue(2 * s + 1, vb + (size_t)u * TILE_BYTES);
                } else {
                    mbar_arrive(bar_full + 16 * s);
                }
                if (!w_done && u >= NU - WTHRESH - TMPF && u < NU - WTHRESH) {
                    asm volatile("prefetch.tensormap [%0];" ::"l"(&tm_w2) : "memory");
                    asm volatile("prefetch.tensormap [%0];" ::"l"(&tm_wo) : "memory");
                }
                if (!w_done && u >= NU - WTHRESH) {
                    TR(3);
                    mbar_expect_tx(bar_w, W2_BYTES);
                    tma_2d(sb + SM_W2, &tm_w2, quart * QCOLS, head * QCOLS, bar_w, pol);
                    mbar_expect_tx(bar_w + 8, WO_BYTES);
                    tma_2d(sb + SM_WO, &tm_wo, quart * QCOLS, head * DH, bar_w + 8, pol);
                }
            }
            if (u >= NU - WTHRESH) w_done = true;
            if (u < NU) *reinterpret_cast<uint2*>(smem + SM_Q + 256 * s + lane * 8) = settle_tagged(qv, qp, tag16);
            __syncwarp();
            if (lane == 0) mbar_arrive(bar_full + 16 * s);
            if (u >= NU) break;
        }
        if (lane == 0) { TR(4); TRDUMP(0); TRDUMP(1); TRDUMP(3); TRDUMP(4); TRDUMP(2); TRDUMP(12); TRDUMP(5); TRDUMP(13); TRDUMP(14);
            for (int i = 16; i < 24; i++) TRDUMP(i);
        }
        __syncwarp();
    } else if (pass == 0) {
        if (warp == 12) continue;
        float* red = reinterpret_cast<float*>(smem + SM_RED);
        uint32_t xf[3][2];
#pragma unroll
        for (int k = 0; k < 3; k++) {
            const unsigned* xp = reinterpret_cast<const unsigned*>(x + g * DM + 48 * warp + 16 * k + 2 * t);
            xf[k][0] = __ldg(xp);
            xf[k][1] = __ldg(xp + 4);
        }
        const unsigned ep_raw = ld_relaxed(&g_epoch.v);
        if (owner) {
            mbar_wait(bar_q + 8 * (warp >> 2), 0);
            float c0[4] = {0.f, 0.f, 0.f, 0.f}, c1[4] = {0.f, 0.f, 0.f, 0.f};
            const uint32_t row = (lane & 7) + (lane >> 4) * 8, ch = (lane >> 3) & 1, sw = (row >> 1) & 3;
            const uint32_t abase = sb + SM_WO + (48 * warp + row) * 64;
#pragma unroll
            for (int k = 0; k < 3; k++) {
                uint32_t a[4], a2[4];
                ldsm4t(a, abase + k * 1024 + ((ch ^ sw) * 16));
                ldsm4t(a2, abase + k * 1024 + (((ch + 2) ^ sw) * 16));
                mma16816(c0, a, xf[k][0], xf[k][1]);
                mma16816(c1, a2, xf[k][0], xf[k][1]);
            }
            float* rp = red + warp * 256 + (2 * t) * 32 + g;
            rp[0] = c0[0]; rp[32] = c0[1]; rp[8] = c0[2]; rp[40] = c0[3];
            rp[16] = c1[0]; rp[48] = c1[1]; rp[24] = c1[2]; rp[56] = c1[3];
        }
        bar_sync(2, 384);
        tag = (ep_raw + 1) & 3u;
        tag16 = ((ep_raw + 1) & 0x7fffu) | 0x8000u;
        if (tid == 0) TR(14);
        if (warp < 8 && owner) {
            float s = 0.f;
#pragma unroll
            for (int w = 0; w < 12; w++) s += red[w * 256 + tid];
            st_relaxed(g_q + warp * (NH * DH) + cta * 32 + lane, tag_bf16(s, tag16));
        }
        if (warp < 8) bar_sync(5, 256);
        if (warp == 9 || warp == 10) {
            const int i = warp - 9;
            const unsigned* qp = g_q + ((cta + i * NCTA) / UPP) * DH + lane * 4;
            *reinterpret_cast<uint2*>(smem + SM_Q + 256 * i + lane * 8) = settle_tagged(ld_relaxed4(qp), qp, tag16);
            __syncwarp();
            if (lane == 0) { mbar_arrive(bar_full + 16 * i); TR(2 + i * 10); }
        }
        if (warp >= 8) continue;
    } else
    if (warp < 8) {
        const bool valid = (t == (g >> 1));
        const bool odd = g & 1;
        const uint32_t r7 = lane & 7;
        const uint32_t koff = (uint32_t)(warp * 16 + r7 + ((lane >> 3) & 1) * 8) * 256, kx = ((lane >> 4) ^ r7) * 16;
        const uint32_t voff = (uint32_t)(warp * 16 + r7 + (lane >> 4) * 8) * 256, vx = (((lane >> 3) & 1) ^ r7) * 16;
        for (int it = 0;; it++) {
            const int s = it & 1;
            const uint32_t ph = (it >> 1) & 1;
            mbar_wait(bar_full + 16 * s, ph);
            const int u = s_unit[s];
            if (u < 0) break;
            if (it == 0 && tid == 0) TR(5);
            const uint32_t kbase = sb + SM_RING + (2 * s) * TILE_BYTES + koff;
            const uint32_t qbase = sb + SM_Q + 256 * s + t * 4;
            float c0[4] = {0.f, 0.f, 0.f, 0.f}, c1[4] = {0.f, 0.f, 0.f, 0.f};
#pragma unroll
            for (int j = 0; j < 8; j += 2) {
                uint32_t a[4], a2[4];
                ldsm4(a, kbase + (kx ^ (j * 32)));
                ldsm4(a2, kbase + (kx ^ ((j + 1) * 32)));
                const uint32_t q0 = lds32(qbase + (((2 * j) ^ g) * 16)), q1 = lds32(qbase + (((2 * j + 1) ^ g) * 16));
                const uint32_t q2 = lds32(qbase + (((2 * j + 2) ^ g) * 16)), q3 = lds32(qbase + (((2 * j + 3) ^ g) * 16));
                mma16816(c0, a, q0, q1);
                mma16816(c1, a2, q2, q3);
            }
            if (lane == 0) mbar_arrive(bar_empty + 16 * s + ((__float_as_uint(c0[0]) | __float_as_uint(c1[0])) & zero));
            const float s0 = odd ? c0[1] + c1[1] : c0[0] + c1[0];
            const float s1 = odd ? c0[3] + c1[3] : c0[2] + c1[2];
            const float m = warp_max(valid ? fmaxf(s0, s1) : -INFINITY);
            const float p0 = valid ? ex2((s0 - m) * SCL) : 0.f;
            const float p1 = valid ? ex2((s1 - m) * SCL) : 0.f;
            const uint32_t b0 = odd ? pack_bf16(0.f, p0) : pack_bf16(p0, 0.f);
            const uint32_t b1 = odd ? pack_bf16(0.f, p1) : pack_bf16(p1, 0.f);
            float l = p0 + p1;
#pragma unroll
            for (int o = 16; o > 0; o >>= 1) l += __shfl_xor_sync(0xffffffffu, l, o);

            mbar_wait(bar_full + 16 * s + 8, ph);
            const uint32_t vbase = sb + SM_RING + (2 * s + 1) * TILE_BYTES + voff;
            float r[8][2];
            uint32_t dep = 0;
#pragma unroll
            for (int j = 0; j < 8; j++) {
                uint32_t a[4];
                ldsm4t(a, vbase + (vx ^ (j * 32)));
                dep |= a[0];
                float c[4] = {0.f, 0.f, 0.f, 0.f};
                mma16816(c, a, b0, b1);
                r[j][0] = c[0] + c[3];
                r[j][1] = c[1] + c[2];
            }
            if (lane == 0) mbar_arrive(bar_empty + 16 * s + 8 + (dep & zero));
#pragma unroll
            for (int j = 0; j < 8; j += 2) {
                r[j][0] += __shfl_xor_sync(0xffffffffu, r[j + 1][0], 1);
                r[j][1] += __shfl_xor_sync(0xffffffffu, r[j + 1][1], 1);
            }
#pragma unroll
            for (int j = 0; j < 8; j += 4) {
                r[j][0] += __shfl_xor_sync(0xffffffffu, r[j + 2][0], 2);
                r[j][1] += __shfl_xor_sync(0xffffffffu, r[j + 2][1], 2);
            }
            float* part = reinterpret_cast<float*>(smem + SM_PART) + s * 1024;
            float* ml = reinterpret_cast<float*>(smem + SM_ML) + s * 16;
            float* pw = part + warp * 128 + 16 * t + g;
            pw[0] = r[0][0]; pw[8] = r[0][1]; pw[64] = r[4][0]; pw[72] = r[4][1];
            if (lane == 0) *reinterpret_cast<float2*>(ml + 2 * warp) = make_float2(m, l);
            bar_sync(5, 256);
            if (warp < 4) {
                float mw[8], lw[8];
#pragma unroll
                for (int w = 0; w < 8; w += 2) {
                    const float4 v = *reinterpret_cast<const float4*>(ml + 2 * w);
                    mw[w] = v.x; lw[w] = v.y; mw[w + 1] = v.z; lw[w + 1] = v.w;
                }
                float M = mw[0];
#pragma unroll
                for (int w = 1; w < 8; w++) M = fmaxf(M, mw[w]);
                float L = 0.f, o = 0.f;
#pragma unroll
                for (int w = 0; w < 8; w++) {
                    const float f = ex2((mw[w] - M) * SCL);
                    L = fmaf(f, lw[w], L);
                    o = fmaf(f, part[w * 128 + tid], o);
                }
                st_relaxed(g_po + (size_t)u * DH + tid, (__float_as_uint(__fdividef(o, L)) & ~3u) | tag);
                if (tid < 8) st_relaxed(g_lse + u * 8 + tid, (__float_as_uint(fmaf(M, SCL, __log2f(L))) & ~3u) | tag);
            }
        }
        if (tid == 0) TR(6);
    } else {
        const int cw = warp - 8, ct = tid - 256;
        {
            {
                long long t0 = clock64();
                while (*s_front == 0) {
                    __nanosleep(200);
                    if (clock64() - t0 > SPIN_LIMIT) __trap();
                }
            }
            const int hs0 = owner ? cta : NOWN + (cta - NOWN) * 4;
            const int nsl = owner ? 1 : 4;
            float* red = reinterpret_cast<float*>(smem + SM_COMB);
#pragma unroll 1
            for (int i = 0; i < nsl; i++) {
                float c0[4] = {0.f, 0.f, 0.f, 0.f}, c1[4] = {0.f, 0.f, 0.f, 0.f};
#pragma unroll 1
                for (int r = 0; r < 3; r++) {
                    Slice sh;
                    uint2 xf[3];
                    slice_load(sh, w1, FF, (hs0 + i) * 32, cw * 3 + r, g, t);
#pragma unroll
                    for (int k = 0; k < 3; k++) xf[k] = ldg64_stream(x + g * DM + 48 * (cw * 3 + r) + 16 * k + 4 * t);
                    slice_mma(sh, xf, c0, c1);
                }
                slice_store(c0, c1, red + cw * 256, g, t);
                bar_sync(7, 128);
#pragma unroll
                for (int e = 0; e < 2; e++) {
                    const int o = ct + e * 128;
                    float s = (red[o] + red[256 + o]) + (red[512 + o] + red[768 + o]);
                    s = bf16_round(s);
                    s = s / (1.f + __expf(-s));
                    st_relaxed(g_h + (o >> 5) * FF + (hs0 + i) * 32 + lane, tag_bf16(s, tag16));
                }
                bar_sync(7, 128);
            }
            if (ct == 0) TR(13);
        }
        if (!owner) return;
        {
            float* gs = reinterpret_cast<float*>(smem + SM_G);
#pragma unroll
            for (int i = 0; i < 2; i++) {
                const int b = 2 * cw + i;
                float s = 0.f;
#pragma unroll
                for (int k = 0; k < DM / 32; k++)
                    s += bf16_round(__bfloat162float(x[b * DM + k * 32 + lane]) * __bfloat162float(gate_w[k * 32 + lane]));
#pragma unroll
                for (int o = 16; o > 0; o >>= 1) s += __shfl_xor_sync(0xffffffffu, s, o);
                s = bf16_round(s);
                if (lane == 0) gs[b] = bf16_round(1.f / (1.f + __expf(-s)));
            }
        }
        for (int b = 0; b < NB; b++) {
            const int pair = b * NH + head;
            {
                const int target = (pair + 1) * UPP + CMARGIN;
                long long t0 = clock64();
                while (*s_front < target) {
                    __nanosleep(200);
                    if (clock64() - t0 > SPIN_LIMIT) __trap();
                }
            }
            if (b == 7 && ct == 0) TR(7);
            const unsigned* lp = g_lse + (size_t)(pair * UPP + lane) * 8;
            const unsigned* op = g_po + (size_t)(pair * UPP + cw * 8) * DH + lane * 4;
            unsigned lb;
            uint4 ov[8];
            {
                long long t0 = clock64();
                for (;;) {
                    lb = ld_relaxed(lp);
#pragma unroll
                    for (int i = 0; i < 8; i++) ov[i] = ld_relaxed4(op + i * DH);
                    unsigned bad = lb ^ tag;
#pragma unroll
                    for (int i = 0; i < 8; i++) bad |= (ov[i].x ^ tag) | (ov[i].y ^ tag) | (ov[i].z ^ tag) | (ov[i].w ^ tag);
                    if (__all_sync(0xffffffffu, (bad & 3u) == 0)) break;
                    if (clock64() - t0 > SPIN_LIMIT) __trap();
                }
            }
            const float lse = __uint_as_float(lb & ~3u);
            const float W = warp_max(lse);
            const float f = ex2(lse - W);
            float Z = f;
#pragma unroll
            for (int o = 16; o > 0; o >>= 1) Z += __shfl_xor_sync(0xffffffffu, Z, o);
            float4 acc = make_float4(0.f, 0.f, 0.f, 0.f);
#pragma unroll
            for (int i = 0; i < 8; i++) {
                const float fi = __shfl_sync(0xffffffffu, f, cw * 8 + i);
                acc.x = fmaf(fi, __uint_as_float(ov[i].x & ~3u), acc.x);
                acc.y = fmaf(fi, __uint_as_float(ov[i].y & ~3u), acc.y);
                acc.z = fmaf(fi, __uint_as_float(ov[i].z & ~3u), acc.z);
                acc.w = fmaf(fi, __uint_as_float(ov[i].w & ~3u), acc.w);
            }
            float* comb = reinterpret_cast<float*>(smem + SM_COMB) + (b & 1) * 512;
            *reinterpret_cast<float4*>(comb + cw * 128 + lane * 4) = acc;
            bar_sync(7, 128);
            const float o = (comb[ct] + comb[128 + ct]) + (comb[256 + ct] + comb[384 + ct]);
            *reinterpret_cast<__nv_bfloat16*>(smem + SM_OS + b * OS_PITCH + ct * 2) = __float2bfloat16_rn(__fdividef(o, Z));
            if (b == 1) {
                for (int i = ct; i < 8 * 36; i += 128) {
                    const int row = i / 36, ch = i % 36;
                    const unsigned* hp = g_h + row * FF + head * QCOLS + ch * 4;
                    *reinterpret_cast<uint2*>(smem + SM_HS + row * HS_PITCH + ch * 8) = settle_tagged(ld_relaxed4(hp), hp, tag16);
                }
                __syncwarp();
                bar_arrive(3, 416);
            }
        }
        if (ct == 0) TR(8);
        __syncwarp();
        bar_arrive(6, 416);
        return;
    }
    if (!owner) { if (pass == 1) return; else continue; }

    {
        const int mt = warp < 8 ? warp : 8;
        const uint32_t aoff = (uint32_t)((lane & 7) + (lane >> 4) * 8) * WPITCH + mt * 32 + ((lane >> 3) & 1) * 16;
        float ca[4] = {0.f, 0.f, 0.f, 0.f}, cb[4] = {0.f, 0.f, 0.f, 0.f}, cc[4] = {0.f, 0.f, 0.f, 0.f};
        const uint32_t ob = sb + SM_OS + g * OS_PITCH + t * 4, hb = sb + SM_HS + g * HS_PITCH + t * 4;
        if (pass == 1) { bar_sync(3, 416); mbar_wait(bar_w, 0); }
#pragma unroll
        for (int k = 0; k < 9; k++) {
            uint32_t a[4];
            ldsm4t(a, sb + SM_W2 + aoff + k * 16 * WPITCH);
            mma16816(cb, a, lds32(hb + k * 32), lds32(hb + k * 32 + 16));
        }
        if (pass == 1) mbar_wait(bar_w + 8, 0);
        uint32_t wf[8][4];
#pragma unroll
        for (int k = 0; k < 8; k++) ldsm4t(wf[k], sb + SM_WO + aoff + k * 16 * WPITCH);
        if (tid == 0) TR(15);
        if (pass == 1) bar_sync(6, 416);
        if (tid == 0) TR(9);
#pragma unroll
        for (int k = 0; k < 8; k += 2) {
            mma16816(ca, wf[k], lds32(ob + k * 32), lds32(ob + k * 32 + 16));
            mma16816(cc, wf[k + 1], lds32(ob + k * 32 + 32), lds32(ob + k * 32 + 48));
        }
#pragma unroll
        for (int i = 0; i < 4; i++) ca[i] += cc[i];
        const float* gs = reinterpret_cast<const float*>(smem + SM_G);
        const float g0 = gs[2 * t], g1 = gs[2 * t + 1];
        const float h0 = bf16_round(1.f - g0), h1 = bf16_round(1.f - g1);
        const float v0 = g0 * ca[0] + h0 * cb[0], v1 = g1 * ca[1] + h1 * cb[1];
        const float v2 = g0 * ca[2] + h0 * cb[2], v3 = g1 * ca[3] + h1 * cb[3];
        if (tid == 0) TR(11);
        float4* ap = g_acc + (quart * 9 + mt) * 64 + lane;
        float4 o0 = make_float4(0.f, 0.f, 0.f, 0.f), o1 = o0;
        if (pass == 1) {
        asm volatile("atom.global.add.v4.f32 {%0,%1,%2,%3}, [%4], {%5,%6,%7,%8};"
                     : "=f"(o0.x), "=f"(o0.y), "=f"(o0.z), "=f"(o0.w) : "l"(ap), "f"(v0), "f"(v1), "f"(1.f), "f"(0.f) : "memory");
        asm volatile("atom.global.add.v4.f32 {%0,%1,%2,%3}, [%4], {%5,%6,%7,%8};"
                     : "=f"(o1.x), "=f"(o1.y), "=f"(o1.z), "=f"(o1.w) : "l"(ap + 32), "f"(v2), "f"(v3), "f"(1.f), "f"(0.f) : "memory");
        }
        __nv_bfloat16* op = out + (2 * t) * DM + quart * QCOLS + mt * 16 + g;
        if (o0.z == (float)(NH - 1)) {
            op[0] = __float2bfloat16_rn(o0.x + v0); op[DM] = __float2bfloat16_rn(o0.y + v1);
            ap[0] = make_float4(0.f, 0.f, 0.f, 0.f);
        }
        if (o1.z == (float)(NH - 1)) {
            op[8] = __float2bfloat16_rn(o1.x + v2); op[DM + 8] = __float2bfloat16_rn(o1.y + v3);
            ap[32] = make_float4(0.f, 0.f, 0.f, 0.f);
        }
    }
    if (tid == 0 && pass == 1) { TR(10); TRDUMP(6); TRDUMP(7); TRDUMP(8); TRDUMP(9); TRDUMP(10); TRDUMP(11); TRDUMP(15); }
    }
}

typedef CUresult (*EncodeFn)(CUtensorMap*, CUtensorMapDataType, cuuint32_t, void*, const cuuint64_t*, const cuuint64_t*,
                             const cuuint32_t*, const cuuint32_t*, CUtensorMapInterleave, CUtensorMapSwizzle,
                             CUtensorMapL2promotion, CUtensorMapFloatOOBfill);

void make_map(EncodeFn fn, CUtensorMap* tm, const void* base, int rows, int cols, int box_rows, int box_cols,
              CUtensorMapSwizzle sw) {
    cuuint64_t dims[2] = {(cuuint64_t)cols, (cuuint64_t)rows};
    cuuint64_t strides[1] = {(cuuint64_t)cols * 2};
    cuuint32_t box[2] = {(cuuint32_t)box_cols, (cuuint32_t)box_rows};
    cuuint32_t estr[2] = {1, 1};
    fn(tm, CU_TENSOR_MAP_DATA_TYPE_BFLOAT16, 2, const_cast<void*>(base), dims, strides, box, estr,
       CU_TENSOR_MAP_INTERLEAVE_NONE, sw, CU_TENSOR_MAP_L2_PROMOTION_NONE,
       CU_TENSOR_MAP_FLOAT_OOB_FILL_NONE);
}

}

extern "C" void kernel_launch(void* const* d_in, const int* in_sizes, int n_in, void* d_out, int out_size) {
    (void)in_sizes; (void)n_in; (void)out_size;
    const __nv_bfloat16* x  = (const __nv_bfloat16*)d_in[0];
    const __nv_bfloat16* kc = (const __nv_bfloat16*)d_in[1];
    const __nv_bfloat16* vc = (const __nv_bfloat16*)d_in[2];
    const __nv_bfloat16* wq = (const __nv_bfloat16*)d_in[3];
    const __nv_bfloat16* wo = (const __nv_bfloat16*)d_in[4];
    const __nv_bfloat16* w1 = (const __nv_bfloat16*)d_in[6];
    const __nv_bfloat16* w2 = (const __nv_bfloat16*)d_in[7];
    const __nv_bfloat16* gw = (const __nv_bfloat16*)d_in[8];

    static EncodeFn encode = nullptr;
    if (!encode) {
        void* fn = nullptr;
        cudaDriverEntryPointQueryResult st;
        cudaGetDriverEntryPoint("cuTensorMapEncodeTiled", &fn, cudaEnableDefault, &st);
        encode = (EncodeFn)fn;
        cudaFuncSetAttribute(fused_kernel, cudaFuncAttributeMaxDynamicSharedMemorySize, SM_TOTAL + SM_EXTRA);
    }
    CUtensorMap tm_wq, tm_wo, tm_w2;
    make_map(encode, &tm_wq, wq, DM, NH * DH, 192, 32, CU_TENSOR_MAP_SWIZZLE_64B);
    make_map(encode, &tm_wo, wo, NH * DH, DM, DH, WBOX, CU_TENSOR_MAP_SWIZZLE_NONE);
    make_map(encode, &tm_w2, w2, FF, DM, QCOLS, WBOX, CU_TENSOR_MAP_SWIZZLE_NONE);
    fused_kernel<<<NCTA, NTHREADS, SM_TOTAL + SM_EXTRA, cudaStreamPerThread>>>(x, kc, vc, w1, gw, (__nv_bfloat16*)d_out, 0u, tm_wq, tm_wo, tm_w2);
}
```

```cpp
#include <cuda_runtime.h>
#include <cuda_bf16.h>
#include <cuda.h>
#include <stdint.h>

namespace {

constexpr int NB = 8, DM = 576, NH = 32, SK = 4096, DH = 128, FF = 4608;
constexpr int TKEYS = 128;
constexpr int TILE_BYTES = TKEYS * DH * 2;
constexpr int UPP = SK / TKEYS;
constexpr int NU = NB * NH * UPP;
constexpr int NCTA = 132, NOWN = 128;
constexpr int NTHREADS = 448;
constexpr int NSTATIC = 4;
constexpr int PACE_T0 = 2400, PACE_DT = 1300;
constexpr int CMARGIN = 528;
constexpr int DRAW_DELAY = 800;
constexpr int DRAW_DELAY_END = 1300, DRAW_END = 300;
constexpr int XMARGIN = 190;
constexpr int EARLY_HEADS = 24;
constexpr int UNIT_NS = 20;
constexpr int W2ROWS = FF / NH;
constexpr int OS_PITCH = 272, HS_PITCH = 304;

constexpr int SM_RING = 0;
constexpr int SM_WO   = 4 * TILE_BYTES;
constexpr int SM_W2   = SM_WO + 2 * DH * 128;
constexpr int SM_WOS  = SM_W2 + 2 * W2ROWS * 128;
constexpr int SM_W2S  = SM_WOS + DH * 32;
constexpr int SM_Q    = SM_W2S + W2ROWS * 32;
constexpr int SM_PART = SM_Q + 512;
constexpr int SM_ML   = SM_PART + 2 * 8 * 128 * 4;
constexpr int SM_OS   = SM_ML + 128;
constexpr int SM_HS   = SM_OS + 8 * OS_PITCH;
constexpr int SM_COMB = SM_HS + 8 * HS_PITCH;
constexpr int SM_G    = SM_COMB + 2 * 4 * 128 * 4 + 512;
constexpr int SM_BAR  = SM_G + 32;
constexpr int SM_MISC = SM_BAR + 20 * 8;
constexpr int SM_TOTAL = SM_MISC + 32;
constexpr int SM_RED  = SM_OS;
constexpr int SM_X    = SM_WO + DM * 64;
static_assert(SM_TOTAL <= 232448, "smem");
static_assert(SM_RED + 9 * 256 * 4 <= SM_G && SM_X + NB * DM * 2 <= SM_WOS, "scratch");

struct __align__(128) Sync { unsigned v; unsigned pad[31]; };
__device__ Sync g_ticket;
__device__ Sync g_epoch;
__device__ __align__(128) unsigned g_q[NB * NH * DH];
__device__ __align__(128) unsigned g_h[NB * FF];
__device__ __align__(128) unsigned g_po[NU * DH];
__device__ __align__(128) unsigned g_lse[NU];
__device__ __align__(128) float4 g_acc[4 * 9 * 2 * 32];

__device__ __forceinline__ unsigned gtime32() { unsigned t; asm volatile("mov.u32 %0, %globaltimer_lo;" : "=r"(t)); return t; }
__device__ __forceinline__ void watchdog(unsigned t0) { if (gtime32() - t0 > 2000000000u) __trap(); }

__device__ __forceinline__ void mbar_init(uint32_t bar, uint32_t cnt) {
    asm volatile("mbarrier.init.shared::cta.b64 [%0], %1;" ::"r"(bar), "r"(cnt) : "memory");
}
__device__ __forceinline__ void mbar_init_fence() { asm volatile("fence.mbarrier_init.release.cluster;" ::: "memory"); }
__device__ __forceinline__ void mbar_expect_tx(uint32_t bar, uint32_t bytes) {
    asm volatile("mbarrier.arrive.expect_tx.shared::cta.b64 _, [%0], %1;" ::"r"(bar), "r"(bytes) : "memory");
}
__device__ __forceinline__ void mbar_arrive(uint32_t bar) {
    asm volatile("mbarrier.arrive.shared::cta.b64 _, [%0];" ::"r"(bar) : "memory");
}
__device__ __forceinline__ bool mbar_try(uint32_t bar, uint32_t parity) {
    uint32_t ok;
    asm volatile("{\n.reg .pred p;\nmbarrier.try_wait.parity.shared::cta.b64 p, [%1], %2;\nselp.u32 %0, 1, 0, p;\n}"
                 : "=r"(ok) : "r"(bar), "r"(parity) : "memory");
    return ok != 0;
}
__device__ __forceinline__ void mbar_wait(uint32_t bar, uint32_t parity) {
    if (mbar_try(bar, parity)) return;
    const unsigned t0 = gtime32();
    while (!mbar_try(bar, parity)) watchdog(t0);
}
__device__ __forceinline__ void mbar_wait_warp(uint32_t bar, uint32_t parity) { mbar_wait(bar, parity); __syncwarp(); }
__device__ __forceinline__ void bulk_g2s(uint32_t dst, const void* src, uint32_t bytes, uint32_t bar, uint64_t pol) {
    asm volatile("cp.async.bulk.shared::cluster.global.mbarrier::complete_tx::bytes.L2::cache_hint [%0], [%1], %2, [%3], %4;"
                 ::"r"(dst), "l"(src), "r"(bytes), "r"(bar), "l"(pol) : "memory");
}
__device__ __forceinline__ void tma_2d(uint32_t dst, const CUtensorMap* tm, int c0, int c1, uint32_t bar, uint64_t pol) {
    asm volatile("cp.async.bulk.tensor.2d.shared::cluster.global.mbarrier::complete_tx::bytes.L2::cache_hint [%0], [%1, {%3, %4}], [%2], %5;"
                 ::"r"(dst), "l"(tm), "r"(bar), "r"(c0), "r"(c1), "l"(pol) : "memory");
}
__device__ __forceinline__ void bar_sync(int id, int n) { __syncwarp(); asm volatile("barrier.sync %0, %1;" ::"r"(id), "r"(n) : "memory"); }
__device__ __forceinline__ void bar_arrive(int id, int n) { __syncwarp(); asm volatile("barrier.arrive %0, %1;" ::"r"(id), "r"(n) : "memory"); }
__device__ __forceinline__ void ldsm4(uint32_t (&r)[4], uint32_t a) {
    asm volatile("ldmatrix.sync.aligned.m8n8.x4.shared.b16 {%0,%1,%2,%3}, [%4];"
                 : "=r"(r[0]), "=r"(r[1]), "=r"(r[2]), "=r"(r[3]) : "r"(a) : "memory");
}
__device__ __forceinline__ void ldsm4t(uint32_t (&r)[4], uint32_t a) {
    asm volatile("ldmatrix.sync.aligned.m8n8.x4.trans.shared.b16 {%0,%1,%2,%3}, [%4];"
                 : "=r"(r[0]), "=r"(r[1]), "=r"(r[2]), "=r"(r[3]) : "r"(a) : "memory");
}
__device__ __forceinline__ void mma16816(float (&c)[4], const uint32_t (&a)[4], uint32_t b0, uint32_t b1) {
    asm volatile("mma.sync.aligned.m16n8k16.row.col.f32.bf16.bf16.f32 {%0,%1,%2,%3}, {%4,%5,%6,%7}, {%8,%9}, {%0,%1,%2,%3};"
                 : "+f"(c[0]), "+f"(c[1]), "+f"(c[2]), "+f"(c[3])
                 : "r"(a[0]), "r"(a[1]), "r"(a[2]), "r"(a[3]), "r"(b0), "r"(b1));
}
__device__ __forceinline__ uint32_t lds32(uint32_t a) {
    uint32_t v; asm volatile("ld.shared.u32 %0, [%1];" : "=r"(v) : "r"(a) : "memory"); return v;
}
__device__ __forceinline__ unsigned ld_relaxed(const unsigned* p) {
    unsigned v; asm volatile("ld.relaxed.gpu.global.u32 %0, [%1];" : "=r"(v) : "l"(p) : "memory"); return v;
}
__device__ __forceinline__ uint4 ld_relaxed4(const void* p) {
    uint4 v; asm volatile("ld.relaxed.gpu.global.v4.u32 {%0,%1,%2,%3}, [%4];"
                          : "=r"(v.x), "=r"(v.y), "=r"(v.z), "=r"(v.w) : "l"(p) : "memory"); return v;
}
__device__ __forceinline__ void st_relaxed(unsigned* p, unsigned v) {
    asm volatile("st.relaxed.gpu.global.u32 [%0], %1;" ::"l"(p), "r"(v) : "memory");
}
__device__ __forceinline__ float4 atom_add4(float4* p, float x, float y, float z) {
    float4 o;
    asm volatile("atom.global.add.v4.f32 {%0,%1,%2,%3}, [%4], {%5,%6,%7,%8};"
                 : "=f"(o.x), "=f"(o.y), "=f"(o.z), "=f"(o.w) : "l"(p), "f"(x), "f"(y), "f"(z), "f"(0.f) : "memory");
    return o;
}
__device__ __forceinline__ float ex2(float x) { float y; asm("ex2.approx.ftz.f32 %0, %1;" : "=f"(y) : "f"(x)); return y; }
__device__ __forceinline__ uint32_t pack_bf16(float lo, float hi) {
    uint32_t r; asm("cvt.rn.bf16x2.f32 %0, %1, %2;" : "=r"(r) : "f"(hi), "f"(lo)); return r;
}
__device__ __forceinline__ float bf16_round(float x) { return __bfloat162float(__float2bfloat16_rn(x)); }
__device__ __forceinline__ float warp_max(float x) {
    int b = __float_as_int(x);
    b ^= (b >> 31) & 0x7fffffff;
    b = __reduce_max_sync(0xffffffffu, b);
    b ^= (b >> 31) & 0x7fffffff;
    return __int_as_float(b);
}
__device__ __forceinline__ float warp_sum(float x) {
#pragma unroll
    for (int o = 16; o > 0; o >>= 1) x += __shfl_xor_sync(0xffffffffu, x, o);
    return x;
}
__device__ __forceinline__ bool tags16_ok(const uint4& v, unsigned tag) {
    return (((v.x ^ tag) | (v.y ^ tag) | (v.z ^ tag) | (v.w ^ tag)) & 0xffffu) == 0;
}
__device__ __forceinline__ uint2 settle_tagged(uint4 v, const unsigned* p, unsigned tag) {
    if (!tags16_ok(v, tag)) {
        const unsigned t0 = gtime32();
        do { v = ld_relaxed4(p); watchdog(t0); } while (!tags16_ok(v, tag));
    }
    return make_uint2(__byte_perm(v.x, v.y, 0x7632), __byte_perm(v.z, v.w, 0x7632));
}
__device__ __forceinline__ unsigned tag_bf16(float x, unsigned tag) {
    return ((unsigned)__bfloat16_as_ushort(__float2bfloat16_rn(x)) << 16) | tag;
}
__device__ __forceinline__ void spin_ns(int ns) {
    const unsigned t0 = gtime32();
    while ((int)(gtime32() - t0) < ns) { }
}

template <int KS>
__device__ __forceinline__ void xw_mma(float (&c0)[4], float (&c1)[4], uint32_t sb, int k0, int lane) {
    const uint32_t row = (lane & 7) + (lane >> 4) * 8, ch = (lane >> 3) & 1, sw = (row >> 1) & 3;
    const uint32_t abase = sb + SM_WO + (k0 + row) * 64;
    const uint32_t xbase = sb + SM_X + ((lane >> 2) * DM + k0 + 2 * (lane & 3)) * 2;
#pragma unroll
    for (int k = 0; k < KS; k++) {
        uint32_t a[4], a2[4];
        ldsm4t(a, abase + k * 1024 + ((ch ^ sw) * 16));
        ldsm4t(a2, abase + k * 1024 + (((ch + 2) ^ sw) * 16));
        const uint32_t x0 = lds32(xbase + k * 32), x1 = lds32(xbase + k * 32 + 16);
        mma16816(c0, a, x0, x1);
        mma16816(c1, a2, x0, x1);
    }
}
__device__ __forceinline__ void xw_store(const float (&c0)[4], const float (&c1)[4], float* red, int lane) {
    float* rp = red + (2 * (lane & 3)) * 32 + (lane >> 2);
    rp[0] = c0[0]; rp[32] = c0[1]; rp[8] = c0[2]; rp[40] = c0[3];
    rp[16] = c1[0]; rp[48] = c1[1]; rp[24] = c1[2]; rp[56] = c1[3];
}

__global__ void __launch_bounds__(NTHREADS, 1)
fused_kernel(const __nv_bfloat16* __restrict__ x, const __nv_bfloat16* __restrict__ kc, const __nv_bfloat16* __restrict__ vc,
             const __nv_bfloat16* __restrict__ gate_w,
             __nv_bfloat16* __restrict__ out, const uint32_t zero,
             const __grid_constant__ CUtensorMap tm_wq, const __grid_constant__ CUtensorMap tm_w1,
             const __grid_constant__ CUtensorMap tm_wo,
             const __grid_constant__ CUtensorMap tm_w2, const __grid_constant__ CUtensorMap tm_wos,
             const __grid_constant__ CUtensorMap tm_w2s)
{
    extern __shared__ __align__(1024) uint8_t smem[];
    const uint32_t sb = (uint32_t)__cvta_generic_to_shared(smem);
    const int warp = threadIdx.x >> 5, lane = threadIdx.x & 31;
    const int cta = blockIdx.x;
    const bool owner = cta < NOWN;
    const int head = cta >> 2, quart = cta & 3;
    const uint32_t bar_full = sb + SM_BAR, bar_empty = bar_full + 32, bar_q = bar_full + 64, bar_x = bar_full + 88, bar_w = bar_full + 96,
                   bar_xd = bar_full + 144;
    volatile int* s_unit = reinterpret_cast<volatile int*>(smem + SM_MISC);
    volatile int* s_front = s_unit + 2;
    constexpr float SCL = 0.08838834764831845f * 1.4426950408889634f;

    uint64_t pol;
    asm volatile("createpolicy.fractional.L2::evict_first.b64 %0, 1.0;" : "=l"(pol));
    const char* kb = reinterpret_cast<const char*>(kc);
    const char* vb = reinterpret_cast<const char*>(vc);
    auto issue = [&](int slot, const char* src) {
        mbar_expect_tx(bar_full + 8 * slot, TILE_BYTES);
        bulk_g2s(sb + SM_RING + slot * TILE_BYTES, src, TILE_BYTES, bar_full + 8 * slot, pol);
    };
    if (threadIdx.x == 0) {
        mbar_init(bar_full, 2);
        mbar_init_fence();
        issue(0, kb + (size_t)cta * TILE_BYTES);
    }
    if (lane == 0) {
        if (warp >= 1 && warp < 4) {
            const int j = warp - 1;
            mbar_init(bar_q + 8 * j, 1);
            mbar_init_fence();
            if (owner) {
                mbar_expect_tx(bar_q + 8 * j, 192 * 64);
                tma_2d(sb + SM_WO + j * (192 * 64), &tm_wq, cta * 32, j * 192, bar_q + 8 * j, pol);
            }
        } else if (warp == 5) {
            mbar_init(bar_x, 1);
            mbar_init_fence();
            mbar_expect_tx(bar_x, NB * DM * 2);
            bulk_g2s(sb + SM_X, x, NB * DM * 2, bar_x, pol);
        } else if (warp == 12) {
#pragma unroll
            for (int s = 1; s < 4; s++) mbar_init(bar_full + 8 * s, (s & 1) ? 1 : 2);
#pragma unroll
            for (int s = 0; s < 4; s++) mbar_init(bar_empty + 8 * s, 8);
#pragma unroll
            for (int s = 0; s < 6; s++) mbar_init(bar_w + 8 * s, 1);
            mbar_init(bar_xd, 4);
            mbar_init_fence();
            *s_front = 0;
            s_unit[0] = cta;
            s_unit[1] = cta + NCTA;
        }
    }
    const unsigned t_start = gtime32();
    const unsigned ep_raw = ld_relaxed(&g_epoch.v);
    bar_sync(1, NTHREADS);
    if (warp == 11) {
        if (lane == 0) {
#pragma unroll 1
            for (int i = 1; i < 4; i++) {
                while ((int)(gtime32() - t_start) < PACE_T0 + (i - 1) * PACE_DT) { }
                issue(i, ((i & 1) ? vb : kb) + (size_t)(cta + (i >> 1) * NCTA) * TILE_BYTES);
            }
        }
        __syncwarp();
    }
    const unsigned epoch = ep_raw + 1;
    const unsigned tag = epoch & 3u, tag16 = epoch & 0xffffu;

#pragma unroll 1
    for (int pass = 0; pass < 2; pass++) {
        const bool dry = pass == 0;
        int tid = threadIdx.x;
        asm volatile("" : "+r"(tid));
        const int warp = tid >> 5, lane = tid & 31, g = lane >> 2, t = lane & 3;
        if (warp == 12) {
            for (int it = 2;; it++) {
                const int s = it & 1;
                const uint32_t ph = ((it >> 1) & 1) ^ 1;
                int u = cta + it * NCTA;
                if (lane == 0 && !dry) {
                    mbar_wait(bar_empty + 16 * s, ph);
                    if (it >= NSTATIC) {
                        spin_ns(*s_front > NU - DRAW_END ? DRAW_DELAY_END : DRAW_DELAY);
                        const unsigned tk = atomicAdd(&g_ticket.v, 1u);
                        u = (int)tk + NSTATIC * NCTA;
                        if (tk == NU - NSTATIC * NCTA + NCTA - 1) {
                            st_relaxed(&g_ticket.v, 0u);
                            st_relaxed(&g_epoch.v, epoch);
                        }
                    }
                    if (u < NU) issue(2 * s, kb + (size_t)u * TILE_BYTES);
                    s_unit[s] = (u < NU) ? u : -1;
                    if (u < NU) s_front[1] = (int)(gtime32() - (unsigned)u * UNIT_NS);
                    *s_front = u;
                }
                u = __shfl_sync(0xffffffffu, u, 0);
                const bool live = u < NU && !dry;
                const unsigned* qp = g_q + (u / UPP) * DH + lane * 4;
                uint4 qv = make_uint4(tag16, tag16, tag16, tag16);
                if (live) qv = ld_relaxed4(qp);
                if (lane == 0 && !dry) {
                    if (live) {
                        mbar_wait(bar_empty + 16 * s + 8, ph);
                        issue(2 * s + 1, vb + (size_t)u * TILE_BYTES);
                    } else {
                        mbar_arrive(bar_full + 16 * s);
                        mbar_arrive(bar_full + 16 * s);
                    }
                }
                if (!live) {
                    const bool is_o = lane == 2 || lane == 3 || lane == 5, small = lane >= 4;
                    const int rows = is_o ? DH : W2ROWS;
                    const CUtensorMap* tm = small ? (is_o ? &tm_wos : &tm_w2s) : (is_o ? &tm_wo : &tm_w2);
                    const uint32_t dst = sb + (small ? (is_o ? SM_WOS : SM_W2S) : (is_o ? SM_WO : SM_W2) + (lane & 1) * rows * 128);
                    if (lane < 6 && owner && !dry) {
                        mbar_wait(bar_xd, 0);
                        mbar_expect_tx(bar_w + 8 * lane, rows * (small ? 32 : 128));
                        tma_2d(dst, tm, small ? 512 + quart * 16 : quart * 128 + (lane & 1) * 64, head * rows, bar_w + 8 * lane, pol);
                    }
                    __syncwarp();
                }
                const uint2 q2 = settle_tagged(qv, qp, tag16);
                if (live) *reinterpret_cast<uint2*>(smem + SM_Q + 256 * s + lane * 8) = q2;
                __syncwarp();
                if (lane == 0 && live) mbar_arrive(bar_full + 16 * s);
                if (!live) break;
            }
            if (dry) continue;
        } else if (dry ? warp == 13 : warp < 8) {
            const int cwarp = warp & 7;
            const bool valid = (t == (g >> 1));
            const bool odd = g & 1;
            const uint32_t r7 = lane & 7;
            const uint32_t koff = (uint32_t)(cwarp * 16 + r7 + ((lane >> 3) & 1) * 8) * 256, kx = ((lane >> 4) ^ r7) * 16;
            const uint32_t voff = (uint32_t)(cwarp * 16 + r7 + (lane >> 4) * 8) * 256, vx = (((lane >> 3) & 1) ^ r7) * 16;
            for (int it = 0;; it++) {
                const int s = it & 1;
                const uint32_t ph = (it >> 1) & 1;
                if (!dry) mbar_wait_warp(bar_full + 16 * s, ph);
                const int u = s_unit[s];
                if (u < 0) break;
                const uint32_t kbase = sb + SM_RING + (2 * s) * TILE_BYTES + koff;
                const uint32_t qbase = sb + SM_Q + 256 * s + t * 4;
                float c0[4] = {0.f, 0.f, 0.f, 0.f}, c1[4] = {0.f, 0.f, 0.f, 0.f};
#pragma unroll
                for (int j = 0; j < 8; j += 2) {
                    uint32_t a[4], a2[4];
                    ldsm4(a, kbase + (kx ^ (j * 32)));
                    ldsm4(a2, kbase + (kx ^ ((j + 1) * 32)));
                    const uint32_t q0 = lds32(qbase + (((2 * j) ^ g) * 16)), q1 = lds32(qbase + (((2 * j + 1) ^ g) * 16));
                    const uint32_t q2 = lds32(qbase + (((2 * j + 2) ^ g) * 16)), q3 = lds32(qbase + (((2 * j + 3) ^ g) * 16));
                    mma16816(c0, a, q0, q1);
                    mma16816(c1, a2, q2, q3);
                }
                if (lane == 0 && !dry) mbar_arrive(bar_empty + 16 * s + ((__float_as_uint(c0[0]) | __float_as_uint(c1[0])) & zero));
                const float s0 = odd ? c0[1] + c1[1] : c0[0] + c1[0];
                const float s1 = odd ? c0[3] + c1[3] : c0[2] + c1[2];
                const float m = warp_max(valid ? fmaxf(s0, s1) : -INFINITY);
                const float p0 = valid ? ex2((s0 - m) * SCL) : 0.f;
                const float p1 = valid ? ex2((s1 - m) * SCL) : 0.f;
                const uint32_t b0 = odd ? pack_bf16(0.f, p0) : pack_bf16(p0, 0.f);
                const uint32_t b1 = odd ? pack_bf16(0.f, p1) : pack_bf16(p1, 0.f);
                const float l = warp_sum(p0 + p1);

                if (!dry) mbar_wait_warp(bar_full + 16 * s + 8, ph);
                const uint32_t vbase = sb + SM_RING + (2 * s + 1) * TILE_BYTES + voff;
                float r[8][2];
                uint32_t dep = 0;
#pragma unroll
                for (int j = 0; j < 8; j++) {
                    uint32_t a[4];
                    ldsm4t(a, vbase + (vx ^ (j * 32)));
                    dep |= a[0];
                    float c[4] = {0.f, 0.f, 0.f, 0.f};
                    mma16816(c, a, b0, b1);
                    r[j][0] = c[0] + c[3];
                    r[j][1] = c[1] + c[2];
                }
                if (lane == 0 && !dry) mbar_arrive(bar_empty + 16 * s + 8 + (dep & zero));
#pragma unroll
                for (int j = 0; j < 8; j += 2) {
                    r[j][0] += __shfl_xor_sync(0xffffffffu, r[j + 1][0], 1);
                    r[j][1] += __shfl_xor_sync(0xffffffffu, r[j + 1][1], 1);
                }
#pragma unroll
                for (int j = 0; j < 8; j += 4) {
                    r[j][0] += __shfl_xor_sync(0xffffffffu, r[j + 2][0], 2);
                    r[j][1] += __shfl_xor_sync(0xffffffffu, r[j + 2][1], 2);
                }
                float* part = reinterpret_cast<float*>(smem + SM_PART) + s * 1024;
                float* ml = reinterpret_cast<float*>(smem + SM_ML) + s * 16;
                float* pw = part + cwarp * 128 + 16 * t + g;
                if (!dry) {
                    pw[0] = r[0][0]; pw[8] = r[0][1]; pw[64] = r[4][0]; pw[72] = r[4][1];
                    if (lane == 0) *reinterpret_cast<float2*>(ml + 2 * cwarp) = make_float2(m, l);
                    bar_sync(5, 256);
                }
                if (warp < 4 || dry) {
                    float mw[8], lw[8];
#pragma unroll
                    for (int w = 0; w < 8; w += 2) {
                        const float4 v = *reinterpret_cast<const float4*>(ml + 2 * w);
                        mw[w] = v.x; lw[w] = v.y; mw[w + 1] = v.z; lw[w + 1] = v.w;
                    }
                    float M = mw[0];
#pragma unroll
                    for (int w = 1; w < 8; w++) M = fmaxf(M, mw[w]);
                    float L = 0.f, o = 0.f;
#pragma unroll
                    for (int w = 0; w < 8; w++) {
                        const float f = ex2((mw[w] - M) * SCL);
                        L = fmaf(f, lw[w], L);
                        o = fmaf(f, part[w * 128 + (tid & 127)], o);
                    }
                    const unsigned ov = (__float_as_uint(__fdividef(o, L)) & ~3u) | tag;
                    const unsigned lv = (__float_as_uint(fmaf(M, SCL, __log2f(L))) & ~3u) | tag;
                    if (!dry) st_relaxed(g_po + (size_t)u * DH + tid, ov);
                    if (!dry && tid == 0) st_relaxed(g_lse + u, lv);
                }
                if (dry) break;
            }
        } else if (!dry) {
            const int cw = warp - 8, ct = tid - 256;
            {
                const unsigned t0 = gtime32();
                while (*s_front == 0) { __nanosleep(200); watchdog(t0); }
            }
            mbar_wait(bar_x, 0);
            {
                const int hs0 = owner ? cta : NOWN + (cta - NOWN) * 4;
                const int nsl = owner ? 1 : 4;
                float* red = reinterpret_cast<float*>(smem + SM_COMB);
#pragma unroll 1
                for (int i = 0; i < nsl; i++) {
                    if (ct < 3) {
                        mbar_expect_tx(bar_q + 8 * ct, 192 * 64);
                        tma_2d(sb + SM_WO + ct * (192 * 64), &tm_w1, (hs0 + i) * 32, ct * 192, bar_q + 8 * ct, pol);
                    }
#pragma unroll
                    for (int j = 0; j < 3; j++) mbar_wait(bar_q + 8 * j, owner ? 1 : i & 1);
                    __syncwarp();
                    float c0[4] = {0.f, 0.f, 0.f, 0.f}, c1[4] = {0.f, 0.f, 0.f, 0.f};
#pragma unroll 1
                    for (int r = 0; r < 3; r++) xw_mma<3>(c0, c1, sb, 144 * cw + 48 * r, lane);
                    xw_store(c0, c1, red + cw * 256, lane);
                    bar_sync(7, 128);
#pragma unroll
                    for (int e = 0; e < 2; e++) {
                        const int o = ct + e * 128;
                        float s = bf16_round((red[o] + red[256 + o]) + (red[512 + o] + red[768 + o]));
                        s = s / (1.f + __expf(-s));
                        st_relaxed(g_h + (o >> 5) * FF + (hs0 + i) * 32 + lane, tag_bf16(s, tag16));
                    }
                    bar_sync(7, 128);
                }
            }
            if (!owner) return;
#pragma unroll 1
            for (int b = 2 * cw; b < 2 * cw + 2; b++) {
                float s = 0.f;
#pragma unroll 2
                for (int k = 0; k < DM / 32; k++)
                    s += bf16_round(__bfloat162float(reinterpret_cast<const __nv_bfloat16*>(smem + SM_X)[b * DM + k * 32 + lane]) *
                                    __bfloat162float(gate_w[k * 32 + lane]));
                s = bf16_round(warp_sum(s));
                if (lane == 0) reinterpret_cast<float*>(smem + SM_G)[b] = bf16_round(1.f / (1.f + __expf(-s)));
            }
            if (lane == 0) mbar_arrive(bar_xd);
#pragma unroll 1
            for (int b = 0; b < NB; b++) {
                const int pair = b * NH + head;
                const unsigned t0 = gtime32();
                for (;;) {
                    const int f = *s_front;
                    if (f >= (pair + 1) * UPP + CMARGIN) break;
                    int left = 1000;
                    if (f >= NU - 200) left = ((pair + 1) * UPP + XMARGIN) * UNIT_NS - (int)(gtime32() - (unsigned)s_front[1]);
                    if (left <= 0) break;
                    if (left > 600) __nanosleep(200);
                    watchdog(t0);
                }
                const unsigned* lp = g_lse + pair * UPP + lane;
                const unsigned* op = g_po + (size_t)(pair * UPP + cw * 8) * DH + lane * 4;
                unsigned lb;
                uint4 ov[8];
                for (;;) {
                    lb = ld_relaxed(lp);
#pragma unroll
                    for (int i = 0; i < 8; i++) ov[i] = ld_relaxed4(op + i * DH);
                    unsigned bad = lb ^ tag;
#pragma unroll
                    for (int i = 0; i < 8; i++) bad |= (ov[i].x ^ tag) | (ov[i].y ^ tag) | (ov[i].z ^ tag) | (ov[i].w ^ tag);
                    if (__all_sync(0xffffffffu, (bad & 3u) == 0)) break;
                    watchdog(t0);
                }
                const float lse = __uint_as_float(lb & ~3u);
                const float f = ex2(lse - warp_max(lse));
                const float Z = warp_sum(f);
                float4 acc = make_float4(0.f, 0.f, 0.f, 0.f);
#pragma unroll
                for (int i = 0; i < 8; i++) {
                    const float fi = __shfl_sync(0xffffffffu, f, cw * 8 + i);
                    acc.x = fmaf(fi, __uint_as_float(ov[i].x & ~3u), acc.x);
                    acc.y = fmaf(fi, __uint_as_float(ov[i].y & ~3u), acc.y);
                    acc.z = fmaf(fi, __uint_as_float(ov[i].z & ~3u), acc.z);
                    acc.w = fmaf(fi, __uint_as_float(ov[i].w & ~3u), acc.w);
                }
                float* comb = reinterpret_cast<float*>(smem + SM_COMB) + (b & 1) * 512;
                *reinterpret_cast<float4*>(comb + cw * 128 + lane * 4) = acc;
                bar_sync(7, 128);
                const float o = (comb[ct] + comb[128 + ct]) + (comb[256 + ct] + comb[384 + ct]);
                *reinterpret_cast<__nv_bfloat16*>(smem + SM_OS + b * OS_PITCH + ct * 2) = __float2bfloat16_rn(__fdividef(o, Z));
                if (b == 3) {
#pragma unroll 1
                    for (int i = ct; i < NB * (W2ROWS / 4); i += 128) {
                        const int row = i / (W2ROWS / 4), ch = i % (W2ROWS / 4);
                        const unsigned* hp = g_h + row * FF + head * W2ROWS + ch * 4;
                        *reinterpret_cast<uint2*>(smem + SM_HS + row * HS_PITCH + ch * 8) = settle_tagged(ld_relaxed4(hp), hp, tag16);
                    }
                }
                if ((b & 3) == 3) bar_arrive(b == 3 ? 3 : 6, 416);
            }
            return;
        }

        if (dry) {
            if (warp <= 8) {
                float* red = reinterpret_cast<float*>(smem + SM_RED);
#pragma unroll 1
                for (int rep = (warp == 8) ? 0 : 1; rep < 2; rep++) {
                    if (rep && owner) { mbar_wait(bar_x, 0); mbar_wait_warp(bar_q + 8 * (warp / 3), 0); }
                    float c0[4] = {0.f, 0.f, 0.f, 0.f}, c1[4] = {0.f, 0.f, 0.f, 0.f};
                    xw_mma<4>(c0, c1, sb, 64 * warp, lane);
                    xw_store(c0, c1, red + warp * 256, lane);
                    if (rep) bar_sync(2, 352);
                    float s = 0.f;
#pragma unroll
                    for (int w = 0; w < 9; w++) s += red[w * 256 + (tid & 255)];
                    if (warp < 8 && owner) st_relaxed(g_q + warp * (NH * DH) + cta * 32 + lane, tag_bf16(s, tag16));
                }
            } else if (warp < 11) {
                const int i = warp - 9;
                const unsigned* qp = g_q + ((cta + i * NCTA) / UPP) * DH + lane * 4;
#pragma unroll 1
                for (int rep = 0; rep < 2; rep++) {
                    uint4 qv = make_uint4(tag16, tag16, tag16, tag16);
                    if (rep) { bar_sync(2, 352); qv = ld_relaxed4(qp); }
                    *reinterpret_cast<uint2*>(smem + SM_Q + 256 * i + lane * 8) = settle_tagged(qv, qp, tag16);
                    __syncwarp();
                    if (rep && lane == 0) mbar_arrive(bar_full + 16 * i);
                }
            }
            if (warp != 13) continue;
        } else if (!owner) {
            return;
        }

        const int mt = warp < 8 ? warp : 8;
        const uint32_t arow = (lane & 7) + (lane >> 4) * 8, ahi = (lane >> 3) & 1;
        const uint32_t aoff = mt < 8 ? arow * 128 + ((((mt & 3) * 2 + ahi) ^ (arow & 7)) * 16) : arow * 32 + ((ahi ^ ((arow >> 2) & 1)) * 16);
        const uint32_t a2 = sb + aoff + (mt < 8 ? SM_W2 + (mt >> 2) * (W2ROWS * 128) : SM_W2S);
        const uint32_t ao = sb + aoff + (mt < 8 ? SM_WO + (mt >> 2) * (DH * 128) : SM_WOS);
        const uint32_t kstep = mt < 8 ? 16 * 128 : 16 * 32;
        const uint32_t ob = sb + SM_OS + g * OS_PITCH + t * 4, hb = sb + SM_HS + g * HS_PITCH + t * 4;
        const uint32_t bar_a = bar_w + (mt < 8 ? 8 * (mt >> 2) : 32), bar_b = bar_w + (mt < 8 ? 16 + 8 * (mt >> 2) : 40);
        if (!dry) bar_sync(3, 416);
        uint32_t hf[9][2], of[8][2], wf[8][4];
#pragma unroll
        for (int k = 0; k < 9; k++) { hf[k][0] = lds32(hb + k * 32); hf[k][1] = lds32(hb + k * 32 + 16); }
        const float g0 = reinterpret_cast<const float*>(smem + SM_G)[2 * t], g1 = reinterpret_cast<const float*>(smem + SM_G)[2 * t + 1];
        const float h0 = bf16_round(1.f - g0), h1 = bf16_round(1.f - g1);
        const bool early = head < EARLY_HEADS && !dry;
        if (early) bar_sync(6, 416);
#pragma unroll
        for (int k = 0; k < 8; k++) { of[k][0] = lds32(ob + k * 32); of[k][1] = lds32(ob + k * 32 + 16); }
        float cb[3][4] = {{0.f, 0.f, 0.f, 0.f}, {0.f, 0.f, 0.f, 0.f}, {0.f, 0.f, 0.f, 0.f}};
        float ca[2][4] = {{0.f, 0.f, 0.f, 0.f}, {0.f, 0.f, 0.f, 0.f}};
        if (!dry) mbar_wait_warp(bar_a, 0);
#pragma unroll
        for (int k = 0; k < 9; k++) {
            uint32_t a[4];
            ldsm4t(a, a2 + k * kstep);
            mma16816(cb[k % 3], a, hf[k][0], hf[k][1]);
        }
        if (!dry) mbar_wait_warp(bar_b, 0);
#pragma unroll
        for (int k = 0; k < 8; k++) ldsm4t(wf[k], ao + k * kstep);
        if (!early) {
            if (!dry) bar_sync(6, 416);
#pragma unroll
            for (int k = 0; k < 8; k++) { of[k][0] = lds32(ob + k * 32); of[k][1] = lds32(ob + k * 32 + 16); }
        }
#pragma unroll
        for (int k = 0; k < 8; k++) mma16816(ca[k & 1], wf[k], of[k][0], of[k][1]);
        const float v0 = fmaf(g0, ca[0][0] + ca[1][0], h0 * (cb[0][0] + cb[1][0] + cb[2][0]));
        const float v1 = fmaf(g1, ca[0][1] + ca[1][1], h1 * (cb[0][1] + cb[1][1] + cb[2][1]));
        const float v2 = fmaf(g0, ca[0][2] + ca[1][2], h0 * (cb[0][2] + cb[1][2] + cb[2][2]));
        const float v3 = fmaf(g1, ca[0][3] + ca[1][3], h1 * (cb[0][3] + cb[1][3] + cb[2][3]));
        float4* ap = g_acc + (quart * 9 + mt) * 64 + lane;
        float4 o0 = make_float4(0.f, 0.f, 0.f, 0.f), o1 = o0;
        if (!dry) {
            o0 = atom_add4(ap, v0, v1, 1.f);
            o1 = atom_add4(ap + 32, v2, v3, 1.f);
        }
        __nv_bfloat16* op = out + (2 * t) * DM + (mt < 8 ? quart * 128 + mt * 16 : 512 + quart * 16) + g;
        if (o0.z == (float)(NH - 1)) {
            op[0] = __float2bfloat16_rn(o0.x + v0); op[DM] = __float2bfloat16_rn(o0.y + v1);
            ap[0] = make_float4(0.f, 0.f, 0.f, 0.f);
        }
        if (o1.z == (float)(NH - 1)) {
            op[8] = __float2bfloat16_rn(o1.x + v2); op[DM + 8] = __float2bfloat16_rn(o1.y + v3);
            ap[32] = make_float4(0.f, 0.f, 0.f, 0.f);
        }
        if (dry) return;
    }
}

typedef CUresult (*EncodeFn)(CUtensorMap*, CUtensorMapDataType, cuuint32_t, void*, const cuuint64_t*, const cuuint64_t*,
                             const cuuint32_t*, const cuuint32_t*, CUtensorMapInterleave, CUtensorMapSwizzle,
                             CUtensorMapL2promotion, CUtensorMapFloatOOBfill);

void make_map(EncodeFn fn, CUtensorMap* tm, const void* base, int rows, int cols, int box_rows, int box_cols,
              CUtensorMapSwizzle sw) {
    cuuint64_t dims[2] = {(cuuint64_t)cols, (cuuint64_t)rows};
    cuuint64_t strides[1] = {(cuuint64_t)cols * 2};
    cuuint32_t box[2] = {(cuuint32_t)box_cols, (cuuint32_t)box_rows};
    cuuint32_t estr[2] = {1, 1};
    fn(tm, CU_TENSOR_MAP_DATA_TYPE_BFLOAT16, 2, const_cast<void*>(base), dims, strides, box, estr,
       CU_TENSOR_MAP_INTERLEAVE_NONE, sw, CU_TENSOR_MAP_L2_PROMOTION_NONE, CU_TENSOR_MAP_FLOAT_OOB_FILL_NONE);
}

}

extern "C" void kernel_launch(void* const* d_in, const int* in_sizes, int n_in, void* d_out, int out_size) {
    (void)in_sizes; (void)n_in; (void)out_size;
    const __nv_bfloat16* x  = (const __nv_bfloat16*)d_in[0];
    const __nv_bfloat16* kc = (const __nv_bfloat16*)d_in[1];
    const __nv_bfloat16* vc = (const __nv_bfloat16*)d_in[2];
    const __nv_bfloat16* wq = (const __nv_bfloat16*)d_in[3];
    const __nv_bfloat16* wo = (const __nv_bfloat16*)d_in[4];
    const __nv_bfloat16* w1 = (const __nv_bfloat16*)d_in[6];
    const __nv_bfloat16* w2 = (const __nv_bfloat16*)d_in[7];
    const __nv_bfloat16* gw = (const __nv_bfloat16*)d_in[8];

    static EncodeFn encode = nullptr;
    if (!encode) {
        void* fn = nullptr;
        cudaDriverEntryPointQueryResult st;
        cudaGetDriverEntryPoint("cuTensorMapEncodeTiled", &fn, cudaEnableDefault, &st);
        encode = (EncodeFn)fn;
        cudaFuncSetAttribute(fused_kernel, cudaFuncAttributeMaxDynamicSharedMemorySize, SM_TOTAL);
    }
    CUtensorMap tm_wq, tm_w1, tm_wo, tm_w2, tm_wos, tm_w2s;
    make_map(encode, &tm_wq, wq, DM, NH * DH, 192, 32, CU_TENSOR_MAP_SWIZZLE_64B);
    make_map(encode, &tm_w1, w1, DM, FF, 192, 32, CU_TENSOR_MAP_SWIZZLE_64B);
    make_map(encode, &tm_wo, wo, NH * DH, DM, DH, 64, CU_TENSOR_MAP_SWIZZLE_128B);
    make_map(encode, &tm_w2, w2, FF, DM, W2ROWS, 64, CU_TENSOR_MAP_SWIZZLE_128B);
    make_map(encode, &tm_wos, wo, NH * DH, DM, DH, 16, CU_TENSOR_MAP_SWIZZLE_32B);
    make_map(encode, &tm_w2s, w2, FF, DM, W2ROWS, 16, CU_TENSOR_MAP_SWIZZLE_32B);
    fused_kernel<<<NCTA, NTHREADS, SM_TOTAL, cudaStreamPerThread>>>(x, kc, vc, gw, (__nv_bfloat16*)d_out, 0u,
                                                                     tm_wq, tm_w1, tm_wo, tm_w2, tm_wos, tm_w2s);
}
```
